```python
import torch

def _softmax(x, axis=-1):
    return torch.softmax(x, dim=axis)
def _gelu(x):
    return torch.nn.functional.gelu(x, approximate="tanh")
def _silu(x):
    return torch.nn.functional.silu(x)
def _sigmoid(x):
    return torch.sigmoid(x)
def _layernorm(x, axis=-1, eps=1e-5):
    m = x.mean(dim=axis, keepdim=True)
    v = x.var(dim=axis, keepdim=True, unbiased=False)
    return (x - m) / torch.sqrt(v + eps)
def _scatter_add(tgt, idx, src, axis=0):
    return tgt.clone().index_add_(axis, idx, src)
def _segment_sum(src, seg, n):
    out = torch.zeros((n,) + src.shape[1:], dtype=src.dtype)
    return out.index_add_(0, seg, src)
def _pad(x, pw):
    flat = tuple(v for pair in reversed(pw) for v in pair)
    return torch.nn.functional.pad(x, flat)

kernel_name = 'gated_mix__linear_kernel_hedgehog__mixer_channel_mlp__prompt'

def setup_inputs():

    _w = (lambda a: (lambda t: t.to(torch.bfloat16) if t.is_floating_point() else t)(torch.as_tensor(a)))
    def _A_setup():
        B, S, D, H = 1, 2048, 1024, 32
        Dh = D // H
        return {
            "x": _w((lambda *s: torch.randn(*s, dtype=torch.bfloat16) * 0.05)(B, S, D)),
            "wqkv": _w((lambda *s: torch.randn(*s, dtype=torch.bfloat16) * 0.8)(D, 3 * D)),
            "w_phi": _w((lambda *s: torch.randn(*s, dtype=torch.bfloat16) * 0.8)(H, Dh, Dh) * (Dh ** -0.5)),
            "wo": _w((lambda *s: torch.randn(*s, dtype=torch.bfloat16) * 0.1)(D, D)),
        }
    _A_in = _A_setup()

    def _B_setup():
        B, S, D, F = 1, 2048, 1024, 3584
        return {
            "x": _w((lambda *s: torch.randn(*s, dtype=torch.bfloat16) * 0.05)(B, S, D)),
            "w1": _w((lambda *s: torch.randn(*s, dtype=torch.bfloat16) * 1.6)(D, F) * (D ** -0.5)),
            "b1": _w((lambda *s: torch.randn(*s, dtype=torch.bfloat16) * 0.4)(F)),
            "w2": _w((lambda *s: torch.randn(*s, dtype=torch.bfloat16) * 0.05)(F, D) * (F ** -0.5)),
            "b2": _w((lambda *s: torch.randn(*s, dtype=torch.bfloat16) * 0.05)(D)),
        }
    _B_in = _B_setup()

    return {
        "A_x": _A_in["x"],
        "A_wqkv": _A_in["wqkv"],
        "A_w_phi": _A_in["w_phi"],
        "A_wo": _A_in["wo"],
        "B_x": _B_in["x"],
        "B_w1": _B_in["w1"],
        "B_b1": _B_in["b1"],
        "B_w2": _B_in["w2"],
        "B_b2": _B_in["b2"],
        "gate_w": _w((lambda *s: torch.randn(*s, dtype=torch.bfloat16) * 0.05)(1024) * 16.0),
    }

def reference(A_x, A_wqkv, A_w_phi, A_wo, B_x, B_w1, B_b1, B_w2, B_b2, gate_w):
    def _A_ref(x, wqkv, w_phi, wo):
        B, S, D = x.shape
        H = 32; Dh = D // H
        qkv = (lambda x, *d: x.permute(*d))((x @ wqkv).reshape(B, S, 3, H, Dh), 2, 0, 3, 1, 4)
        q, k, v = qkv[0], qkv[1], qkv[2]
        pq = torch.einsum("bhsd,hdf->bhsf", q, w_phi)
        pk = torch.einsum("bhsd,hdf->bhsf", k, w_phi)
        phi_q = torch.concatenate([_softmax(pq, axis=-1), _softmax(-pq, axis=-1)], axis=-1)
        phi_k = torch.concatenate([_softmax(pk, axis=-1), _softmax(-pk, axis=-1)], axis=-1)
        kv = torch.einsum("bhsf,bhsd->bhfd", phi_k, v)
        z  = torch.einsum("bhsf->bhf", phi_k)
        num = torch.einsum("bhqf,bhfd->bhqd", phi_q, kv)
        den = torch.einsum("bhqf,bhf->bhq", phi_q, z)[..., None] + 1e-6
        o = num / den
        return (lambda x, *d: x.permute(*d))(o, 0, 2, 1, 3).reshape(B, S, D) @ wo

    def _B_ref(x, w1, b1, w2, b2):
        y = _layernorm(x, axis=-1)
        h = _gelu(torch.einsum("bsd,df->bsf", y, w1) + b1)
        return torch.einsum("bsf,fd->bsd", h, w2) + b2

    x = A_x
    g = _sigmoid((x * gate_w).sum(-1, keepdims=True))
    a = _A_ref(x, A_wqkv, A_w_phi, A_wo)
    b = _B_ref(x, B_w1, B_b1, B_w2, B_b2)
    return g * a + (1 - g) * b
```

```cpp
#include <cuda_runtime.h>
#include <cuda_bf16.h>
#include <cuda.h>
#include <stdint.h>

namespace gm {

constexpr int S = 2048, D = 1024, F = 3584, KHO = F + D;
constexpr int NCTA = 128;
constexpr int NTHREADS = 512;
constexpr int NPRE = 3;
constexpr int LEAD256 = 2, LEAD192 = 2, LEAD_Q = 2, LEAD_OUT = 4;

constexpr uint32_t RING = 0;
constexpr uint32_t WPHI1 = 147456;
constexpr uint32_t STG = 163840;
constexpr uint32_t KVIMG = STG + 32768;
constexpr uint32_t WPHI2 = STG + 53248;
constexpr uint32_t MISC = STG + 65536;
constexpr uint32_t BARS = MISC;
constexpr uint32_t GVEC = MISC + 384;
constexpr uint32_t B2S = MISC + 2048;
constexpr uint32_t ONES = MISC + 1024;
constexpr uint32_t SMEM_BYTES = MISC + 2048 + 256;

enum { B_FULL256 = 0, B_EMPTY256 = 6, B_FULL192 = 12, B_EMPTY192 = 16, B_FULL128 = 20, B_EMPTY128 = 25,
       B_STG_FULL = 30, B_STG_EMPTY = 31, B_AUX = 32, B_E1DONE = 33, B_FLAG = 34  ,
       B_EO = 39  , B_ECONS = 40  , B_EST = 41  ,
       B_LNW = 42, B_E1W = 43, B_RW = 44, B_KVPR = 45,
       B_KVFR = 46  , B_COUNT = 47 };

__device__ __align__(1024) __nv_bfloat16 g_y[S * D];
__device__ __align__(1024) __nv_bfloat16 g_ho[S * KHO];
__device__ __align__(1024) float g_gate[S];
__device__ __align__(1024) float g_kvp[16 * 32 * 64 * 32];
__device__ __align__(1024) float g_zp[16 * 32 * 64];
__device__ __align__(1024) __nv_bfloat16 g_kvimg[32 * 40 * 64];
__device__ __align__(1024) unsigned g_flags[96 * 32];
__device__ __align__(1024) unsigned g_epoch[NCTA];
enum { FL_LN = 0, FL_KVP = 16, FL_KVF = 24, FL_H2 = 32, FL_H3 = 48, FL_O = 64 };

struct Maps {
  CUtensorMap x32, y32, wkv32, w1a32, x, y, ho, wq, w1b, w2, wo;
};
struct Ptrs {
  const __nv_bfloat16 *ax, *gate_w, *b1, *b2, *wphi;
  void* out;
};

__device__ __forceinline__ uint32_t smem_u32(const void* p) { return (uint32_t)__cvta_generic_to_shared(p); }
__device__ __forceinline__ void mbar_init(uint32_t bar, uint32_t count) {
  asm volatile("mbarrier.init.shared::cta.b64 [%0], %1;" ::"r"(bar), "r"(count) : "memory");
}
__device__ __forceinline__ void mbar_expect_tx(uint32_t bar, uint32_t bytes) {
  asm volatile("mbarrier.arrive.expect_tx.shared::cta.b64 _, [%0], %1;" ::"r"(bar), "r"(bytes) : "memory");
}
__device__ __forceinline__ void mbar_arrive(uint32_t bar) {
  asm volatile("mbarrier.arrive.shared::cta.b64 _, [%0];" ::"r"(bar) : "memory");
}
__device__ __forceinline__ bool mbar_try(uint32_t bar, uint32_t parity) {
  uint32_t done;
  asm volatile("{\n.reg .pred p;\nmbarrier.try_wait.parity.shared::cta.b64 p, [%1], %2;\nselp.u32 %0, 1, 0, p;\n}\n"
               : "=r"(done) : "r"(bar), "r"(parity) : "memory");
  return done != 0;
}
constexpr long long WAIT_LIMIT = 2000000000ll;
__device__ __forceinline__ void mbar_wait(uint32_t bar, uint32_t parity, int& dead) {
  if (mbar_try(bar, parity)) return;
  if (dead) return;
  const long long t0 = clock64();
  while (!mbar_try(bar, parity)) {
    if (clock64() - t0 > WAIT_LIMIT) { dead = 1; break; }
  }
}
__device__ __forceinline__ void wait_flag(const unsigned* p, unsigned target, int& dead) {
  const long long t0 = clock64();
  while (!dead) {
    unsigned v;
    asm volatile("ld.acquire.gpu.global.u32 %0, [%1];" : "=r"(v) : "l"(p) : "memory");
    if ((int)(v - target) >= 0) break;
    if (clock64() - t0 > WAIT_LIMIT) dead = 1;
    __nanosleep(40);
  }
}
__device__ __forceinline__ void signal_flag(unsigned* p) {
  asm volatile("red.release.gpu.global.add.u32 [%0], 1;" ::"l"(p) : "memory");
}
__device__ __forceinline__ void fence_async_global() { asm volatile("fence.proxy.async.global;" ::: "memory"); }
__device__ __forceinline__ void fence_async_smem() { asm volatile("fence.proxy.async.shared::cta;" ::: "memory"); }
__device__ __forceinline__ void tma_load(uint32_t dst, const CUtensorMap* m, uint32_t bar, int c0, int c1) {
  asm volatile("cp.async.bulk.tensor.2d.shared::cluster.global.mbarrier::complete_tx::bytes [%0], [%1, {%3, %4}], [%2];"
               ::"r"(dst), "l"(m), "r"(bar), "r"(c0), "r"(c1) : "memory");
}
__device__ __forceinline__ void tma_load3(uint32_t dst, const CUtensorMap* m, uint32_t bar, int c1, int c2) {
  asm volatile("cp.async.bulk.tensor.3d.shared::cluster.global.mbarrier::complete_tx::bytes [%0], [%1, {%3, %4, %5}], [%2];"
               ::"r"(dst), "l"(m), "r"(bar), "r"(0), "r"(c1), "r"(c2) : "memory");
}
__device__ __forceinline__ void tma_load4(uint32_t dst, const CUtensorMap* m, uint32_t bar, int c1, int c2) {
  asm volatile("cp.async.bulk.tensor.4d.shared::cluster.global.mbarrier::complete_tx::bytes [%0], [%1, {%3, %4, %5, %3}], [%2];"
               ::"r"(dst), "l"(m), "r"(bar), "r"(0), "r"(c1), "r"(c2) : "memory");
}
__device__ __forceinline__ void cp_async16(uint32_t dst, const void* src) {
  asm volatile("cp.async.cg.shared.global [%0], [%1], 16;" ::"r"(dst), "l"(src) : "memory");
}
__device__ __forceinline__ void cp_async_arrive(uint32_t bar) {
  asm volatile("cp.async.mbarrier.arrive.noinc.shared::cta.b64 [%0];" ::"r"(bar) : "memory");
}
__device__ __forceinline__ void load_wphi(uint32_t dst, const __nv_bfloat16* src, int lane) {
#pragma unroll 4
  for (int i = 0; i < 16; i++) {
    const int ch = i * 32 + lane, r = ch >> 2, c = ch & 3;
    cp_async16(dst + r * 64 + ((c ^ ((r >> 1) & 3)) << 4), reinterpret_cast<const char*>(src) + ch * 16);
  }
}
__device__ __forceinline__ void prefetch_map(const CUtensorMap* m) {
  asm volatile("prefetch.tensormap [%0];" ::"l"(m) : "memory");
}
__device__ __forceinline__ bool elect_one() {
  uint32_t p;
  asm volatile("{\n.reg .pred P;\nelect.sync _|P, 0xffffffff;\nselp.u32 %0, 1, 0, P;\n}\n" : "=r"(p));
  return p != 0;
}
__device__ __forceinline__ void wg_fence() { asm volatile("wgmma.fence.sync.aligned;" ::: "memory"); }
__device__ __forceinline__ void wg_commit() { asm volatile("wgmma.commit_group.sync.aligned;" ::: "memory"); }
template <int N> __device__ __forceinline__ void wg_wait() {
  asm volatile("wgmma.wait_group.sync.aligned %0;" ::"n"(N) : "memory");
}
__device__ __forceinline__ void named_bar(int id) { asm volatile("bar.sync %0, 128;" ::"r"(id) : "memory"); }
__device__ __forceinline__ void stsm4(uint32_t addr, uint32_t r0, uint32_t r1, uint32_t r2, uint32_t r3) {
  asm volatile("stmatrix.sync.aligned.m8n8.x4.shared.b16 [%0], {%1, %2, %3, %4};"
               ::"r"(addr), "r"(r0), "r"(r1), "r"(r2), "r"(r3) : "memory");
}
__device__ __forceinline__ void ldsm4(uint32_t addr, uint32_t (&r)[4]) {
  asm volatile("ldmatrix.sync.aligned.m8n8.x4.shared.b16 {%0, %1, %2, %3}, [%4];"
               : "=r"(r[0]), "=r"(r[1]), "=r"(r[2]), "=r"(r[3]) : "r"(addr) : "memory");
}
__device__ __forceinline__ void ldsm4t(uint32_t addr, uint32_t (&r)[4]) {
  asm volatile("ldmatrix.sync.aligned.m8n8.x4.trans.shared.b16 {%0, %1, %2, %3}, [%4];"
               : "=r"(r[0]), "=r"(r[1]), "=r"(r[2]), "=r"(r[3]) : "r"(addr) : "memory");
}
__device__ __forceinline__ uint32_t pack_bf16(float lo, float hi) {
  uint32_t r;
  asm("cvt.rn.bf16x2.f32 %0, %1, %2;" : "=r"(r) : "f"(hi), "f"(lo));
  return r;
}
__device__ __forceinline__ uint32_t add_bf16x2(uint32_t a, uint32_t b) {
  uint32_t r;
  asm("add.rn.bf16x2 %0, %1, %2;" : "=r"(r) : "r"(a), "r"(b));
  return r;
}
__device__ __forceinline__ float bf_lo(uint32_t v) { return __uint_as_float(v << 16); }
__device__ __forceinline__ float bf_hi(uint32_t v) { return __uint_as_float(v & 0xffff0000u); }
__device__ __forceinline__ float ex2(float x) {
  float r;
  asm("ex2.approx.ftz.f32 %0, %1;" : "=f"(r) : "f"(x));
  return r;
}
__device__ __forceinline__ float rcp(float x) {
  float r;
  asm("rcp.approx.ftz.f32 %0, %1;" : "=f"(r) : "f"(x));
  return r;
}
__device__ __forceinline__ uint64_t make_desc(uint32_t addr, uint32_t lbo, uint32_t sbo, uint32_t swz) {
  return (uint64_t)((addr & 0x3FFFF) >> 4) | ((uint64_t)(lbo >> 4) << 16) | ((uint64_t)(sbo >> 4) << 32) |
         ((uint64_t)swz << 62);
}
template <int N> __device__ __forceinline__ void reg_fence(float* d) {
#pragma unroll
  for (int i = 0; i < N; i++) asm volatile("" : "+f"(d[i])::"memory");
}

__device__ __forceinline__ void wgmma_ss_n128_init(float* d, uint64_t da, uint64_t db) {
  asm volatile("{\n.reg .pred p;\nsetp.ne.b32 p, 0, 0;\n"
    "wgmma.mma_async.sync.aligned.m64n128k16.f32.bf16.bf16 "
    "{%0, %1, %2, %3, %4, %5, %6, %7, %8, %9, %10, %11, %12, %13, %14, %15, %16, %17, %18, %19, %20, %21, %22, %23, %24, %25, %26, %27, %28, %29, %30, %31, %32, %33, %34, %35, %36, %37, %38, %39, %40, %41, %42, %43, %44, %45, %46, %47, %48, %49, %50, %51, %52, %53, %54, %55, %56, %57, %58, %59, %60, %61, %62, %63}, %64, %65, p, 1, 1, 0, 1;\n}\n"
    : "=f"(d[0]), "=f"(d[1]), "=f"(d[2]), "=f"(d[3]), "=f"(d[4]), "=f"(d[5]), "=f"(d[6]), "=f"(d[7]), "=f"(d[8]), "=f"(d[9]), "=f"(d[10]), "=f"(d[11]), "=f"(d[12]), "=f"(d[13]), "=f"(d[14]), "=f"(d[15]), "=f"(d[16]), "=f"(d[17]), "=f"(d[18]), "=f"(d[19]), "=f"(d[20]), "=f"(d[21]), "=f"(d[22]), "=f"(d[23]), "=f"(d[24]), "=f"(d[25]), "=f"(d[26]), "=f"(d[27]), "=f"(d[28]), "=f"(d[29]), "=f"(d[30]), "=f"(d[31]), "=f"(d[32]), "=f"(d[33]), "=f"(d[34]), "=f"(d[35]), "=f"(d[36]), "=f"(d[37]), "=f"(d[38]), "=f"(d[39]), "=f"(d[40]), "=f"(d[41]), "=f"(d[42]), "=f"(d[43]), "=f"(d[44]), "=f"(d[45]), "=f"(d[46]), "=f"(d[47]), "=f"(d[48]), "=f"(d[49]), "=f"(d[50]), "=f"(d[51]), "=f"(d[52]), "=f"(d[53]), "=f"(d[54]), "=f"(d[55]), "=f"(d[56]), "=f"(d[57]), "=f"(d[58]), "=f"(d[59]), "=f"(d[60]), "=f"(d[61]), "=f"(d[62]), "=f"(d[63])
    : "l"(da), "l"(db));
}
__device__ __forceinline__ void wgmma_ss_n160_init(float* d, uint64_t da, uint64_t db) {
  asm volatile("{\n.reg .pred p;\nsetp.ne.b32 p, 0, 0;\n"
    "wgmma.mma_async.sync.aligned.m64n160k16.f32.bf16.bf16 "
    "{%0, %1, %2, %3, %4, %5, %6, %7, %8, %9, %10, %11, %12, %13, %14, %15, %16, %17, %18, %19, %20, %21, %22, %23, %24, %25, %26, %27, %28, %29, %30, %31, %32, %33, %34, %35, %36, %37, %38, %39, %40, %41, %42, %43, %44, %45, %46, %47, %48, %49, %50, %51, %52, %53, %54, %55, %56, %57, %58, %59, %60, %61, %62, %63, %64, %65, %66, %67, %68, %69, %70, %71, %72, %73, %74, %75, %76, %77, %78, %79}, %80, %81, p, 1, 1, 0, 1;\n}\n"
    : "=f"(d[0]), "=f"(d[1]), "=f"(d[2]), "=f"(d[3]), "=f"(d[4]), "=f"(d[5]), "=f"(d[6]), "=f"(d[7]), "=f"(d[8]), "=f"(d[9]), "=f"(d[10]), "=f"(d[11]), "=f"(d[12]), "=f"(d[13]), "=f"(d[14]), "=f"(d[15]), "=f"(d[16]), "=f"(d[17]), "=f"(d[18]), "=f"(d[19]), "=f"(d[20]), "=f"(d[21]), "=f"(d[22]), "=f"(d[23]), "=f"(d[24]), "=f"(d[25]), "=f"(d[26]), "=f"(d[27]), "=f"(d[28]), "=f"(d[29]), "=f"(d[30]), "=f"(d[31]), "=f"(d[32]), "=f"(d[33]), "=f"(d[34]), "=f"(d[35]), "=f"(d[36]), "=f"(d[37]), "=f"(d[38]), "=f"(d[39]), "=f"(d[40]), "=f"(d[41]), "=f"(d[42]), "=f"(d[43]), "=f"(d[44]), "=f"(d[45]), "=f"(d[46]), "=f"(d[47]), "=f"(d[48]), "=f"(d[49]), "=f"(d[50]), "=f"(d[51]), "=f"(d[52]), "=f"(d[53]), "=f"(d[54]), "=f"(d[55]), "=f"(d[56]), "=f"(d[57]), "=f"(d[58]), "=f"(d[59]), "=f"(d[60]), "=f"(d[61]), "=f"(d[62]), "=f"(d[63]), "=f"(d[64]), "=f"(d[65]), "=f"(d[66]), "=f"(d[67]), "=f"(d[68]), "=f"(d[69]), "=f"(d[70]), "=f"(d[71]), "=f"(d[72]), "=f"(d[73]), "=f"(d[74]), "=f"(d[75]), "=f"(d[76]), "=f"(d[77]), "=f"(d[78]), "=f"(d[79])
    : "l"(da), "l"(db));
}
__device__ __forceinline__ void wgmma_ss_n192_init(float* d, uint64_t da, uint64_t db) {
  asm volatile("{\n.reg .pred p;\nsetp.ne.b32 p, 0, 0;\n"
    "wgmma.mma_async.sync.aligned.m64n192k16.f32.bf16.bf16 "
    "{%0, %1, %2, %3, %4, %5, %6, %7, %8, %9, %10, %11, %12, %13, %14, %15, %16, %17, %18, %19, %20, %21, %22, %23, %24, %25, %26, %27, %28, %29, %30, %31, %32, %33, %34, %35, %36, %37, %38, %39, %40, %41, %42, %43, %44, %45, %46, %47, %48, %49, %50, %51, %52, %53, %54, %55, %56, %57, %58, %59, %60, %61, %62, %63, %64, %65, %66, %67, %68, %69, %70, %71, %72, %73, %74, %75, %76, %77, %78, %79, %80, %81, %82, %83, %84, %85, %86, %87, %88, %89, %90, %91, %92, %93, %94, %95}, %96, %97, p, 1, 1, 0, 1;\n}\n"
    : "=f"(d[0]), "=f"(d[1]), "=f"(d[2]), "=f"(d[3]), "=f"(d[4]), "=f"(d[5]), "=f"(d[6]), "=f"(d[7]), "=f"(d[8]), "=f"(d[9]), "=f"(d[10]), "=f"(d[11]), "=f"(d[12]), "=f"(d[13]), "=f"(d[14]), "=f"(d[15]), "=f"(d[16]), "=f"(d[17]), "=f"(d[18]), "=f"(d[19]), "=f"(d[20]), "=f"(d[21]), "=f"(d[22]), "=f"(d[23]), "=f"(d[24]), "=f"(d[25]), "=f"(d[26]), "=f"(d[27]), "=f"(d[28]), "=f"(d[29]), "=f"(d[30]), "=f"(d[31]), "=f"(d[32]), "=f"(d[33]), "=f"(d[34]), "=f"(d[35]), "=f"(d[36]), "=f"(d[37]), "=f"(d[38]), "=f"(d[39]), "=f"(d[40]), "=f"(d[41]), "=f"(d[42]), "=f"(d[43]), "=f"(d[44]), "=f"(d[45]), "=f"(d[46]), "=f"(d[47]), "=f"(d[48]), "=f"(d[49]), "=f"(d[50]), "=f"(d[51]), "=f"(d[52]), "=f"(d[53]), "=f"(d[54]), "=f"(d[55]), "=f"(d[56]), "=f"(d[57]), "=f"(d[58]), "=f"(d[59]), "=f"(d[60]), "=f"(d[61]), "=f"(d[62]), "=f"(d[63]), "=f"(d[64]), "=f"(d[65]), "=f"(d[66]), "=f"(d[67]), "=f"(d[68]), "=f"(d[69]), "=f"(d[70]), "=f"(d[71]), "=f"(d[72]), "=f"(d[73]), "=f"(d[74]), "=f"(d[75]), "=f"(d[76]), "=f"(d[77]), "=f"(d[78]), "=f"(d[79]), "=f"(d[80]), "=f"(d[81]), "=f"(d[82]), "=f"(d[83]), "=f"(d[84]), "=f"(d[85]), "=f"(d[86]), "=f"(d[87]), "=f"(d[88]), "=f"(d[89]), "=f"(d[90]), "=f"(d[91]), "=f"(d[92]), "=f"(d[93]), "=f"(d[94]), "=f"(d[95])
    : "l"(da), "l"(db));
}
__device__ __forceinline__ void wgmma_rs_n32_tb1_init(float* d, uint32_t a0, uint32_t a1, uint32_t a2, uint32_t a3, uint64_t db) {
  asm volatile("{\n.reg .pred p;\nsetp.ne.b32 p, 0, 0;\n"
    "wgmma.mma_async.sync.aligned.m64n32k16.f32.bf16.bf16 "
    "{%0, %1, %2, %3, %4, %5, %6, %7, %8, %9, %10, %11, %12, %13, %14, %15}, {%16, %17, %18, %19}, %20, p, 1, 1, 1;\n}\n"
    : "=f"(d[0]), "=f"(d[1]), "=f"(d[2]), "=f"(d[3]), "=f"(d[4]), "=f"(d[5]), "=f"(d[6]), "=f"(d[7]), "=f"(d[8]), "=f"(d[9]), "=f"(d[10]), "=f"(d[11]), "=f"(d[12]), "=f"(d[13]), "=f"(d[14]), "=f"(d[15])
    : "r"(a0), "r"(a1), "r"(a2), "r"(a3), "l"(db));
}
__device__ __forceinline__ void wgmma_rs_n40_tb1_init(float* d, uint32_t a0, uint32_t a1, uint32_t a2, uint32_t a3, uint64_t db) {
  asm volatile("{\n.reg .pred p;\nsetp.ne.b32 p, 0, 0;\n"
    "wgmma.mma_async.sync.aligned.m64n40k16.f32.bf16.bf16 "
    "{%0, %1, %2, %3, %4, %5, %6, %7, %8, %9, %10, %11, %12, %13, %14, %15, %16, %17, %18, %19}, {%20, %21, %22, %23}, %24, p, 1, 1, 1;\n}\n"
    : "=f"(d[0]), "=f"(d[1]), "=f"(d[2]), "=f"(d[3]), "=f"(d[4]), "=f"(d[5]), "=f"(d[6]), "=f"(d[7]), "=f"(d[8]), "=f"(d[9]), "=f"(d[10]), "=f"(d[11]), "=f"(d[12]), "=f"(d[13]), "=f"(d[14]), "=f"(d[15]), "=f"(d[16]), "=f"(d[17]), "=f"(d[18]), "=f"(d[19])
    : "r"(a0), "r"(a1), "r"(a2), "r"(a3), "l"(db));
}
__device__ __forceinline__ void wgmma_rs_n40_tb0_init(float* d, uint32_t a0, uint32_t a1, uint32_t a2, uint32_t a3, uint64_t db) {
  asm volatile("{\n.reg .pred p;\nsetp.ne.b32 p, 0, 0;\n"
    "wgmma.mma_async.sync.aligned.m64n40k16.f32.bf16.bf16 "
    "{%0, %1, %2, %3, %4, %5, %6, %7, %8, %9, %10, %11, %12, %13, %14, %15, %16, %17, %18, %19}, {%20, %21, %22, %23}, %24, p, 1, 1, 0;\n}\n"
    : "=f"(d[0]), "=f"(d[1]), "=f"(d[2]), "=f"(d[3]), "=f"(d[4]), "=f"(d[5]), "=f"(d[6]), "=f"(d[7]), "=f"(d[8]), "=f"(d[9]), "=f"(d[10]), "=f"(d[11]), "=f"(d[12]), "=f"(d[13]), "=f"(d[14]), "=f"(d[15]), "=f"(d[16]), "=f"(d[17]), "=f"(d[18]), "=f"(d[19])
    : "r"(a0), "r"(a1), "r"(a2), "r"(a3), "l"(db));
}
__device__ __forceinline__ void wgmma_ss_n128(float* d, uint64_t da, uint64_t db) {
  asm volatile("{\n.reg .pred p;\nsetp.ne.b32 p, 1, 0;\n"
    "wgmma.mma_async.sync.aligned.m64n128k16.f32.bf16.bf16 "
    "{%0, %1, %2, %3, %4, %5, %6, %7, %8, %9, %10, %11, %12, %13, %14, %15, %16, %17, %18, %19, %20, %21, %22, %23, %24, %25, %26, %27, %28, %29, %30, %31, %32, %33, %34, %35, %36, %37, %38, %39, %40, %41, %42, %43, %44, %45, %46, %47, %48, %49, %50, %51, %52, %53, %54, %55, %56, %57, %58, %59, %60, %61, %62, %63}, %64, %65, p, 1, 1, 0, 1;\n}\n"
    : "+f"(d[0]), "+f"(d[1]), "+f"(d[2]), "+f"(d[3]), "+f"(d[4]), "+f"(d[5]), "+f"(d[6]), "+f"(d[7]), "+f"(d[8]), "+f"(d[9]), "+f"(d[10]), "+f"(d[11]), "+f"(d[12]), "+f"(d[13]), "+f"(d[14]), "+f"(d[15]), "+f"(d[16]), "+f"(d[17]), "+f"(d[18]), "+f"(d[19]), "+f"(d[20]), "+f"(d[21]), "+f"(d[22]), "+f"(d[23]), "+f"(d[24]), "+f"(d[25]), "+f"(d[26]), "+f"(d[27]), "+f"(d[28]), "+f"(d[29]), "+f"(d[30]), "+f"(d[31]), "+f"(d[32]), "+f"(d[33]), "+f"(d[34]), "+f"(d[35]), "+f"(d[36]), "+f"(d[37]), "+f"(d[38]), "+f"(d[39]), "+f"(d[40]), "+f"(d[41]), "+f"(d[42]), "+f"(d[43]), "+f"(d[44]), "+f"(d[45]), "+f"(d[46]), "+f"(d[47]), "+f"(d[48]), "+f"(d[49]), "+f"(d[50]), "+f"(d[51]), "+f"(d[52]), "+f"(d[53]), "+f"(d[54]), "+f"(d[55]), "+f"(d[56]), "+f"(d[57]), "+f"(d[58]), "+f"(d[59]), "+f"(d[60]), "+f"(d[61]), "+f"(d[62]), "+f"(d[63])
    : "l"(da), "l"(db));
}
__device__ __forceinline__ void wgmma_ss_n160(float* d, uint64_t da, uint64_t db) {
  asm volatile("{\n.reg .pred p;\nsetp.ne.b32 p, 1, 0;\n"
    "wgmma.mma_async.sync.aligned.m64n160k16.f32.bf16.bf16 "
    "{%0, %1, %2, %3, %4, %5, %6, %7, %8, %9, %10, %11, %12, %13, %14, %15, %16, %17, %18, %19, %20, %21, %22, %23, %24, %25, %26, %27, %28, %29, %30, %31, %32, %33, %34, %35, %36, %37, %38, %39, %40, %41, %42, %43, %44, %45, %46, %47, %48, %49, %50, %51, %52, %53, %54, %55, %56, %57, %58, %59, %60, %61, %62, %63, %64, %65, %66, %67, %68, %69, %70, %71, %72, %73, %74, %75, %76, %77, %78, %79}, %80, %81, p, 1, 1, 0, 1;\n}\n"
    : "+f"(d[0]), "+f"(d[1]), "+f"(d[2]), "+f"(d[3]), "+f"(d[4]), "+f"(d[5]), "+f"(d[6]), "+f"(d[7]), "+f"(d[8]), "+f"(d[9]), "+f"(d[10]), "+f"(d[11]), "+f"(d[12]), "+f"(d[13]), "+f"(d[14]), "+f"(d[15]), "+f"(d[16]), "+f"(d[17]), "+f"(d[18]), "+f"(d[19]), "+f"(d[20]), "+f"(d[21]), "+f"(d[22]), "+f"(d[23]), "+f"(d[24]), "+f"(d[25]), "+f"(d[26]), "+f"(d[27]), "+f"(d[28]), "+f"(d[29]), "+f"(d[30]), "+f"(d[31]), "+f"(d[32]), "+f"(d[33]), "+f"(d[34]), "+f"(d[35]), "+f"(d[36]), "+f"(d[37]), "+f"(d[38]), "+f"(d[39]), "+f"(d[40]), "+f"(d[41]), "+f"(d[42]), "+f"(d[43]), "+f"(d[44]), "+f"(d[45]), "+f"(d[46]), "+f"(d[47]), "+f"(d[48]), "+f"(d[49]), "+f"(d[50]), "+f"(d[51]), "+f"(d[52]), "+f"(d[53]), "+f"(d[54]), "+f"(d[55]), "+f"(d[56]), "+f"(d[57]), "+f"(d[58]), "+f"(d[59]), "+f"(d[60]), "+f"(d[61]), "+f"(d[62]), "+f"(d[63]), "+f"(d[64]), "+f"(d[65]), "+f"(d[66]), "+f"(d[67]), "+f"(d[68]), "+f"(d[69]), "+f"(d[70]), "+f"(d[71]), "+f"(d[72]), "+f"(d[73]), "+f"(d[74]), "+f"(d[75]), "+f"(d[76]), "+f"(d[77]), "+f"(d[78]), "+f"(d[79])
    : "l"(da), "l"(db));
}
__device__ __forceinline__ void wgmma_ss_n192(float* d, uint64_t da, uint64_t db) {
  asm volatile("{\n.reg .pred p;\nsetp.ne.b32 p, 1, 0;\n"
    "wgmma.mma_async.sync.aligned.m64n192k16.f32.bf16.bf16 "
    "{%0, %1, %2, %3, %4, %5, %6, %7, %8, %9, %10, %11, %12, %13, %14, %15, %16, %17, %18, %19, %20, %21, %22, %23, %24, %25, %26, %27, %28, %29, %30, %31, %32, %33, %34, %35, %36, %37, %38, %39, %40, %41, %42, %43, %44, %45, %46, %47, %48, %49, %50, %51, %52, %53, %54, %55, %56, %57, %58, %59, %60, %61, %62, %63, %64, %65, %66, %67, %68, %69, %70, %71, %72, %73, %74, %75, %76, %77, %78, %79, %80, %81, %82, %83, %84, %85, %86, %87, %88, %89, %90, %91, %92, %93, %94, %95}, %96, %97, p, 1, 1, 0, 1;\n}\n"
    : "+f"(d[0]), "+f"(d[1]), "+f"(d[2]), "+f"(d[3]), "+f"(d[4]), "+f"(d[5]), "+f"(d[6]), "+f"(d[7]), "+f"(d[8]), "+f"(d[9]), "+f"(d[10]), "+f"(d[11]), "+f"(d[12]), "+f"(d[13]), "+f"(d[14]), "+f"(d[15]), "+f"(d[16]), "+f"(d[17]), "+f"(d[18]), "+f"(d[19]), "+f"(d[20]), "+f"(d[21]), "+f"(d[22]), "+f"(d[23]), "+f"(d[24]), "+f"(d[25]), "+f"(d[26]), "+f"(d[27]), "+f"(d[28]), "+f"(d[29]), "+f"(d[30]), "+f"(d[31]), "+f"(d[32]), "+f"(d[33]), "+f"(d[34]), "+f"(d[35]), "+f"(d[36]), "+f"(d[37]), "+f"(d[38]), "+f"(d[39]), "+f"(d[40]), "+f"(d[41]), "+f"(d[42]), "+f"(d[43]), "+f"(d[44]), "+f"(d[45]), "+f"(d[46]), "+f"(d[47]), "+f"(d[48]), "+f"(d[49]), "+f"(d[50]), "+f"(d[51]), "+f"(d[52]), "+f"(d[53]), "+f"(d[54]), "+f"(d[55]), "+f"(d[56]), "+f"(d[57]), "+f"(d[58]), "+f"(d[59]), "+f"(d[60]), "+f"(d[61]), "+f"(d[62]), "+f"(d[63]), "+f"(d[64]), "+f"(d[65]), "+f"(d[66]), "+f"(d[67]), "+f"(d[68]), "+f"(d[69]), "+f"(d[70]), "+f"(d[71]), "+f"(d[72]), "+f"(d[73]), "+f"(d[74]), "+f"(d[75]), "+f"(d[76]), "+f"(d[77]), "+f"(d[78]), "+f"(d[79]), "+f"(d[80]), "+f"(d[81]), "+f"(d[82]), "+f"(d[83]), "+f"(d[84]), "+f"(d[85]), "+f"(d[86]), "+f"(d[87]), "+f"(d[88]), "+f"(d[89]), "+f"(d[90]), "+f"(d[91]), "+f"(d[92]), "+f"(d[93]), "+f"(d[94]), "+f"(d[95])
    : "l"(da), "l"(db));
}
__device__ __forceinline__ void wgmma_rs_n32_tb1(float* d, uint32_t a0, uint32_t a1, uint32_t a2, uint32_t a3, uint64_t db) {
  asm volatile("{\n.reg .pred p;\nsetp.ne.b32 p, 1, 0;\n"
    "wgmma.mma_async.sync.aligned.m64n32k16.f32.bf16.bf16 "
    "{%0, %1, %2, %3, %4, %5, %6, %7, %8, %9, %10, %11, %12, %13, %14, %15}, {%16, %17, %18, %19}, %20, p, 1, 1, 1;\n}\n"
    : "+f"(d[0]), "+f"(d[1]), "+f"(d[2]), "+f"(d[3]), "+f"(d[4]), "+f"(d[5]), "+f"(d[6]), "+f"(d[7]), "+f"(d[8]), "+f"(d[9]), "+f"(d[10]), "+f"(d[11]), "+f"(d[12]), "+f"(d[13]), "+f"(d[14]), "+f"(d[15])
    : "r"(a0), "r"(a1), "r"(a2), "r"(a3), "l"(db));
}
__device__ __forceinline__ void wgmma_rs_n40_tb1(float* d, uint32_t a0, uint32_t a1, uint32_t a2, uint32_t a3, uint64_t db) {
  asm volatile("{\n.reg .pred p;\nsetp.ne.b32 p, 1, 0;\n"
    "wgmma.mma_async.sync.aligned.m64n40k16.f32.bf16.bf16 "
    "{%0, %1, %2, %3, %4, %5, %6, %7, %8, %9, %10, %11, %12, %13, %14, %15, %16, %17, %18, %19}, {%20, %21, %22, %23}, %24, p, 1, 1, 1;\n}\n"
    : "+f"(d[0]), "+f"(d[1]), "+f"(d[2]), "+f"(d[3]), "+f"(d[4]), "+f"(d[5]), "+f"(d[6]), "+f"(d[7]), "+f"(d[8]), "+f"(d[9]), "+f"(d[10]), "+f"(d[11]), "+f"(d[12]), "+f"(d[13]), "+f"(d[14]), "+f"(d[15]), "+f"(d[16]), "+f"(d[17]), "+f"(d[18]), "+f"(d[19])
    : "r"(a0), "r"(a1), "r"(a2), "r"(a3), "l"(db));
}
__device__ __forceinline__ void wgmma_rs_n40_tb0(float* d, uint32_t a0, uint32_t a1, uint32_t a2, uint32_t a3, uint64_t db) {
  asm volatile("{\n.reg .pred p;\nsetp.ne.b32 p, 1, 0;\n"
    "wgmma.mma_async.sync.aligned.m64n40k16.f32.bf16.bf16 "
    "{%0, %1, %2, %3, %4, %5, %6, %7, %8, %9, %10, %11, %12, %13, %14, %15, %16, %17, %18, %19}, {%20, %21, %22, %23}, %24, p, 1, 1, 0;\n}\n"
    : "+f"(d[0]), "+f"(d[1]), "+f"(d[2]), "+f"(d[3]), "+f"(d[4]), "+f"(d[5]), "+f"(d[6]), "+f"(d[7]), "+f"(d[8]), "+f"(d[9]), "+f"(d[10]), "+f"(d[11]), "+f"(d[12]), "+f"(d[13]), "+f"(d[14]), "+f"(d[15]), "+f"(d[16]), "+f"(d[17]), "+f"(d[18]), "+f"(d[19])
    : "r"(a0), "r"(a1), "r"(a2), "r"(a3), "l"(db));
}

template <bool V> struct Flag { static constexpr bool value = V; };
template <int GEO>
__device__ __forceinline__ void mma_tile(float* acc, uint32_t sb, int w, int nsteps, int& slot, uint32_t& ph, int& dead, int rel,
                                         int lead) {
  constexpr int NSLOT = GEO == 0 ? 6 : (GEO == 1 ? 4 : 5);
  constexpr uint32_t SLOT = GEO == 0 ? 24576 : (GEO == 1 ? 40960 : 32768);
  constexpr int BF = GEO == 0 ? B_FULL256 : (GEO == 1 ? B_FULL192 : B_FULL128);
  constexpr int BE = GEO == 0 ? B_EMPTY256 : (GEO == 1 ? B_EMPTY192 : B_EMPTY128);
  const uint32_t bars = sb + BARS;
  const int phys0 = GEO == 0 ? (slot >= 4 ? slot - 4 : slot + 2) : slot;
  const uint32_t sa0 = sb + RING + phys0 * SLOT;
  uint64_t da = GEO == 0 ? make_desc(sa0 + w * 4096, 16, 512, 2) : make_desc(sa0 + w * 8192, 16, 1024, 1);
  uint64_t db = GEO == 0 ? make_desc(sa0 + 8192, 4096, 1024, 1) : make_desc(sa0 + 16384, 8192, 1024, 1);
  uint32_t fb = bars + (BF + slot) * 8;
  uint32_t prev_eb = 0;
  auto step = [&](auto first_tag) {
    constexpr bool FIRST = decltype(first_tag)::value;
    mbar_wait(fb, ph, dead);
    wg_fence();
    if (GEO == 0) {
      if (FIRST) { wgmma_ss_n128_init(acc, da, db); wgmma_ss_n128_init(acc + 64, da, db + (8192 >> 4)); }
      else { wgmma_ss_n128(acc, da, db); wgmma_ss_n128(acc + 64, da, db + (8192 >> 4)); }
      wgmma_ss_n128(acc, da + 2, db + 128);
      wgmma_ss_n128(acc + 64, da + 2, db + 128 + (8192 >> 4));
    } else if (GEO == 1) {
      if (FIRST) wgmma_ss_n192_init(acc, da, db); else wgmma_ss_n192(acc, da, db);
#pragma unroll
      for (int s = 1; s < 4; s++) wgmma_ss_n192(acc, da + s * 2, db + s * 128);
    } else {
      if (FIRST) wgmma_ss_n128_init(acc, da, db); else wgmma_ss_n128(acc, da, db);
#pragma unroll
      for (int s = 1; s < 4; s++) wgmma_ss_n128(acc, da + s * 2, db + s * 128);
    }
    wg_commit();
    const uint32_t eb = fb + (BE - BF) * 8;
    slot++;
    fb += 8; da += SLOT >> 4; db += SLOT >> 4;
    if (GEO == 0 && slot == 4) { da -= (NSLOT * SLOT) >> 4; db -= (NSLOT * SLOT) >> 4; }
    if (slot == NSLOT) {
      slot = 0; ph ^= 1; fb -= NSLOT * 8;
      if (GEO != 0) { da -= (NSLOT * SLOT) >> 4; db -= (NSLOT * SLOT) >> 4; }
    }
    if (!FIRST) {
      wg_wait<1>();
      if (rel) mbar_arrive(prev_eb);
    }
    prev_eb = eb;
  };
  step(Flag<true>());
#pragma unroll 1
  for (int k = 1; k < nsteps; k++) {
    if (w == 1 && k == nsteps - lead) asm volatile("bar.sync 6, 256;" ::: "memory");
    step(Flag<false>());
  }
  if (w == 0) asm volatile("bar.arrive 6, 256;" ::: "memory");
  wg_wait<0>();
  if (rel) mbar_arrive(prev_eb);
}

template <int I0, int I1>
__device__ __forceinline__ void dump_tile(const float* acc, uint32_t stg, int wq, int lane, bool vsplit) {
  asm volatile("" : "+r"(lane), "+r"(wq));
  const int r = wq * 16 + (lane & 7) + ((lane >> 3) & 1) * 8;
  const int hi = lane >> 4;
  uint32_t xo[4];
  if (I0 == 8 && vsplit) {
    const uint32_t vb = stg + r * 64;
    const int sw = (r >> 1) & 3;
    xo[0] = vb + (((0 + hi) ^ sw) << 4); xo[1] = vb + (((2 + hi) ^ sw) << 4);
    xo[2] = xo[0] + 8192; xo[3] = xo[1] + 8192;
  } else {
#pragma unroll
    for (int i = 0; i < 4; i++) xo[i] = stg + r * 128 + (((2 * i + hi) ^ (lane & 7)) << 4);
  }
#pragma unroll
  for (int i = I0; i < I1; i++) {
    const float* a = acc + 8 * (i - I0);
    stsm4(xo[i & 3] + (i >> 2) * 16384, pack_bf16(a[0], a[1]), pack_bf16(a[2], a[3]), pack_bf16(a[4], a[5]), pack_bf16(a[6], a[7]));
  }
}

__device__ __forceinline__ void project_and_dump(const float* acc, uint32_t sb, uint32_t wphi, int wq, int lane) {
  float p[4][16];
  uint32_t a[4][2][4];
#pragma unroll
  for (int h = 0; h < 4; h++)
#pragma unroll
    for (int s = 0; s < 2; s++)
#pragma unroll
      for (int e = 0; e < 4; e++) a[h][s][e] = pack_bf16(acc[16 * h + 8 * s + 2 * e], acc[16 * h + 8 * s + 2 * e + 1]);
  fence_async_smem();
  wg_fence();
#pragma unroll
  for (int h = 0; h < 4; h++) {
    const uint64_t db = make_desc(wphi + h * 2048, 2048, 512, 2);
    wgmma_rs_n32_tb1_init(p[h], a[h][0][0], a[h][0][1], a[h][0][2], a[h][0][3], db);
    wgmma_rs_n32_tb1(p[h], a[h][1][0], a[h][1][1], a[h][1][2], a[h][1][3], db + 64);
  }
  wg_commit();
  wg_wait<0>();
#pragma unroll
  for (int h = 0; h < 4; h++) reg_fence<16>(p[h]);
  dump_tile<0, 8>(&p[0][0], sb + STG, wq, lane, false);
}

template <int U>
__device__ __forceinline__ void dual_softmax(float (&p)[U][16], uint32_t (&P)[U][4][2], uint32_t (&Nn)[U][4][2]) {
  constexpr float L2E = 1.4426950408889634f;
  float mx[U][2], mn[U][2];
#pragma unroll
  for (int u = 0; u < U; u++)
#pragma unroll
    for (int i = 0; i < 2; i++) {
      float a = p[u][2 * i], b = p[u][2 * i];
#pragma unroll
      for (int k = 1; k < 8; k++) {
        const float v = p[u][4 * (k >> 1) + 2 * i + (k & 1)];
        a = fmaxf(a, v); b = fminf(b, v);
      }
      mx[u][i] = a; mn[u][i] = b;
    }
#pragma unroll
  for (int o = 1; o <= 2; o <<= 1)
#pragma unroll
    for (int u = 0; u < U; u++)
#pragma unroll
      for (int i = 0; i < 2; i++) {
        mx[u][i] = fmaxf(mx[u][i], __shfl_xor_sync(0xffffffffu, mx[u][i], o));
        mn[u][i] = fminf(mn[u][i], __shfl_xor_sync(0xffffffffu, mn[u][i], o));
      }
  float en[U][16], sp[U][2], sn[U][2];
#pragma unroll
  for (int u = 0; u < U; u++)
#pragma unroll
    for (int i = 0; i < 2; i++) {
      const float cx = -mx[u][i] * L2E, cn = mn[u][i] * L2E;
      float a = 0.f, b = 0.f;
#pragma unroll
      for (int k = 0; k < 8; k++) {
        const int idx = 4 * (k >> 1) + 2 * i + (k & 1);
        const float v = p[u][idx];
        p[u][idx] = ex2(fmaf(v, L2E, cx));
        en[u][idx] = ex2(fmaf(v, -L2E, cn));
        a += p[u][idx]; b += en[u][idx];
      }
      sp[u][i] = a; sn[u][i] = b;
    }
#pragma unroll
  for (int o = 1; o <= 2; o <<= 1)
#pragma unroll
    for (int u = 0; u < U; u++)
#pragma unroll
      for (int i = 0; i < 2; i++) {
        sp[u][i] += __shfl_xor_sync(0xffffffffu, sp[u][i], o);
        sn[u][i] += __shfl_xor_sync(0xffffffffu, sn[u][i], o);
      }
#pragma unroll
  for (int u = 0; u < U; u++)
#pragma unroll
    for (int i = 0; i < 2; i++) {
      const float ip = rcp(sp[u][i]), in = rcp(sn[u][i]);
#pragma unroll
      for (int b = 0; b < 4; b++) {
        P[u][b][i] = pack_bf16(p[u][4 * b + 2 * i] * ip, p[u][4 * b + 2 * i + 1] * ip);
        Nn[u][b][i] = pack_bf16(en[u][4 * b + 2 * i] * in, en[u][4 * b + 2 * i + 1] * in);
      }
    }
}

__device__ __forceinline__ float gelu_tanh(float x, float hs) {
  constexpr float C0 = 0.7978845608028654f;
  constexpr float C1 = C0 * 0.044715f;
  float t;
  asm("tanh.approx.f32 %0, %1;" : "=f"(t) : "f"(x * fmaf(x * x, C1, C0)));
  const float hx = x * hs;
  return fmaf(hx, t, hx);
}

__device__ __forceinline__ void epi_gelu(uint32_t sb, uint32_t bars, const __nv_bfloat16* b1, __nv_bfloat16* dst, int col0, int NCH,
                                         int rel_c, int t) {
  const int q = t >> 5, lane = t & 31;
  const int cc = lane & 7;
  const int r0 = q * 4 + (lane >> 3);
  const uint32_t a0 = sb + STG + r0 * 128 + ((cc ^ (r0 & 7)) << 4);
  dst += (size_t)r0 * KHO + col0 + cc * 8;
  float s1[8];
  uint4 cur[8], nxt[8];
#pragma unroll
  for (int p = 0; p < 8; p++) {
    asm volatile("ld.shared.v4.u32 {%0, %1, %2, %3}, [%4];" : "=r"(cur[p].x), "=r"(cur[p].y), "=r"(cur[p].z), "=r"(cur[p].w) : "r"(a0 + p * 2048));
    asm volatile("ld.shared.f32 %0, [%1];" : "=f"(s1[p]) : "r"(sb + GVEC + (r0 + p * 16) * 4));
  }
  uint4 bv = __ldg(reinterpret_cast<const uint4*>(b1 + col0 + cc * 8));
#pragma unroll
  for (int p = 0; p < 8; p++) s1[p] = 0.5f - 0.5f * s1[p];
#pragma unroll 1
  for (int c = 0; c < NCH; c++) {
    const uint32_t ac = a0 + c * 16384;
    const uint4 bias = bv;
    if (c + 1 < NCH) {
      bv = __ldg(reinterpret_cast<const uint4*>(b1 + col0 + (c + 1) * 64 + cc * 8));
#pragma unroll
      for (int p = 0; p < 8; p++)
        asm volatile("ld.shared.v4.u32 {%0, %1, %2, %3}, [%4];" : "=r"(nxt[p].x), "=r"(nxt[p].y), "=r"(nxt[p].z), "=r"(nxt[p].w) : "r"(ac + 16384 + p * 2048));
    }
#pragma unroll
    for (int p = 0; p < 8; p++) {
      const float s = s1[p];
      uint4 v;
      const uint32_t x0 = add_bf16x2(cur[p].x, bias.x), x1 = add_bf16x2(cur[p].y, bias.y);
      const uint32_t x2 = add_bf16x2(cur[p].z, bias.z), x3 = add_bf16x2(cur[p].w, bias.w);
      v.x = pack_bf16(gelu_tanh(bf_lo(x0), s), gelu_tanh(bf_hi(x0), s));
      v.y = pack_bf16(gelu_tanh(bf_lo(x1), s), gelu_tanh(bf_hi(x1), s));
      v.z = pack_bf16(gelu_tanh(bf_lo(x2), s), gelu_tanh(bf_hi(x2), s));
      v.w = pack_bf16(gelu_tanh(bf_lo(x3), s), gelu_tanh(bf_hi(x3), s));
      *reinterpret_cast<uint4*>(dst + (size_t)p * 16 * KHO + c * 64) = v;
    }
#pragma unroll
    for (int p = 0; p < 8; p++) {
      cur[p] = nxt[p];
      asm volatile("" : "+r"(cur[p].x), "+r"(cur[p].y), "+r"(cur[p].z), "+r"(cur[p].w));
    }
    if (c + 1 == rel_c || c + 1 == NCH - 1) {
      __syncwarp();
      if (lane == 0) {
        if (c + 1 == rel_c) mbar_arrive(bars + B_STG_EMPTY * 8);
        if (c + 1 == NCH - 1) mbar_arrive(bars + B_ECONS * 8);
      }
    }
  }
  __syncwarp();
  if (lane == 0) mbar_arrive(bars + B_EST * 8);
}

__global__ void __launch_bounds__(NTHREADS, 1)
fused_kernel(const __grid_constant__ Maps maps, const Ptrs ptrs) {
  extern __shared__ __align__(1024) uint8_t smem_raw[];
  const uint32_t sb = __shfl_sync(0xffffffffu, smem_u32(smem_raw), 0);
  const uint32_t bars = sb + BARS;
  const int tid = threadIdx.x;
  const int warp = __shfl_sync(0xffffffffu, tid >> 5, 0);
  const int wg = warp >> 2;
  const int wb = blockIdx.x;
  const int pidx = wb >> 3, ms = pidx >> 2, jp = (ms & 1) ? 3 - (pidx & 3) : (pidx & 3);
  const int m_ = ms * 4 + (wb & 3), j_ = jp * 2 + ((wb >> 2) & 1);
  const int mj = __shfl_sync(0xffffffffu, m_ * 8 + j_, 0);
  const int m = mj >> 3, j = mj & 7;
  int dead = 0;

  if (warp == 0) {
    if (elect_one()) {
      prefetch_map(&maps.x32); prefetch_map(&maps.wkv32);
#pragma unroll
      for (int i = 0; i < 6; i++) mbar_init(bars + (B_FULL256 + i) * 8, 2);
    }
    __syncwarp();
#pragma unroll 1
    for (int n = 0; n < NPRE; n++) {
      const uint32_t fb0 = bars + (B_FULL256 + n) * 8;
      const uint32_t a = sb + RING + (n + 2) * 24576, b = a + 8192;
      if (elect_one()) {
        mbar_expect_tx(fb0, 8192);
        mbar_expect_tx(fb0, 16384);
        tma_load(a, &maps.x32, fb0, n * 32, m * 128);
        tma_load4(b, &maps.wkv32, fb0, n * 32, j * 2);
      }
    }
    asm volatile("bar.arrive 0, 512;" ::: "memory");
  } else {
#pragma unroll
    for (int i = 0; i < 3; i++) {
      const int id = 6 + (warp - 1) + i * 15;
      const bool is_empty = (id >= B_EMPTY256 && id < B_FULL192) || (id >= B_EMPTY192 && id < B_FULL128) ||
                            (id >= B_EMPTY128 && id < B_STG_FULL);
      const bool from_epi = id >= B_EO && id <= B_RW;
      const bool is_full = (id >= B_FULL192 && id < B_EMPTY192) || (id >= B_FULL128 && id < B_EMPTY128);
      if (id < B_COUNT && elect_one())
        mbar_init(bars + id * 8, (is_full || is_empty) ? 2 : (id == B_STG_FULL ? 8 : ((from_epi || id == B_STG_EMPTY) ? 4 : (id == B_AUX ? 32 : 1))));
    }
    asm volatile("bar.arrive 4, 512;" ::: "memory");
  }

  if (wg == 0) {
    asm volatile("setmaxnreg.dec.sync.aligned.u32 24;");
    if (warp == 0) {
#pragma unroll 1
      for (int n = NPRE; n < 6; n++) {
        const uint32_t fb0 = bars + (B_FULL256 + n) * 8;
        const uint32_t a = sb + RING + (n >= 4 ? n - 4 : n + 2) * 24576, b = a + 8192;
        if (elect_one()) {
          mbar_expect_tx(fb0, 8192);
          mbar_expect_tx(fb0, 16384);
          tma_load(a, &maps.x32, fb0, n * 32, m * 128);
          tma_load4(b, &maps.wkv32, fb0, n * 32, j * 2);
        }
      }
      asm volatile("bar.sync 4, 512;" ::: "memory");
    } else {
      asm volatile("bar.sync 0, 512;" ::: "memory");
    }
    if (warp == 1) {
      const int lane = tid & 31;
      if (lane < (int)(sizeof(Maps) / sizeof(CUtensorMap))) prefetch_map(reinterpret_cast<const CUtensorMap*>(&maps) + lane);
      if (lane == 0) {
        const unsigned e1 = *(volatile unsigned*)&g_epoch[wb] + 1;
        mbar_wait(bars + B_LNW * 8, 0, dead);
        wait_flag(&g_flags[(FL_LN + m) * 32], e1 * 8, dead);
        fence_async_global();
        mbar_arrive(bars + (B_FLAG + 0) * 8);
        mbar_wait(bars + B_EST * 8, 0, dead);
        wait_flag(&g_flags[(FL_H2 + m) * 32], e1 * 8, dead);
        fence_async_global();
        mbar_arrive(bars + (B_FLAG + 1) * 8);
        mbar_wait(bars + B_EST * 8, 1, dead);
        wait_flag(&g_flags[(FL_H3 + m) * 32], e1 * 8, dead);
        fence_async_global();
        mbar_arrive(bars + (B_FLAG + 2) * 8);
        mbar_wait(bars + B_EO * 8, 0, dead);
        wait_flag(&g_flags[(FL_O + m) * 32], e1 * 8, dead);
        fence_async_global();
        mbar_arrive(bars + (B_FLAG + 3) * 8);
        g_epoch[wb] = e1;
      }
    } else if (warp == 2) {
      {
        const int lane = tid & 31;
        unsigned epoch = 0;
        if (lane == 0) epoch = *(volatile unsigned*)&g_epoch[wb];
        mbar_wait(bars + (B_FULL256 + 5) * 8, 0, dead);
        load_wphi(sb + WPHI1, ptrs.wphi + j * 128 * 32, lane);
        cp_async_arrive(bars + B_AUX * 8);
        if (lane == 0) {
          mbar_wait(bars + B_LNW * 8, 0, dead);
          signal_flag(&g_flags[(FL_LN + m) * 32]);
          mbar_wait(bars + B_E1W * 8, 0, dead);
          mbar_arrive(bars + B_E1DONE * 8);
          signal_flag(&g_flags[(FL_KVP + j) * 32]);
          wait_flag(&g_flags[(FL_KVP + j) * 32], (epoch + 1) * 16, dead);
          mbar_arrive(bars + B_KVPR * 8);
          mbar_wait(bars + B_ECONS * 8, 0, dead);
        }
        __syncwarp();
        load_wphi(sb + WPHI2, ptrs.wphi + j * 128 * 32, lane);
        cp_async_arrive(bars + B_AUX * 8);
        if (lane == 0) {
          mbar_wait(bars + B_EST * 8, 0, dead);
          signal_flag(&g_flags[(FL_H2 + m) * 32]);
          mbar_wait(bars + B_RW * 8, 0, dead);
          signal_flag(&g_flags[(FL_KVF + j) * 32]);
          wait_flag(&g_flags[(FL_KVF + j) * 32], (epoch + 1) * 16, dead);
          mbar_arrive(bars + B_KVFR * 8);
          mbar_wait(bars + B_EST * 8, 1, dead);
          signal_flag(&g_flags[(FL_H3 + m) * 32]);
          mbar_wait(bars + B_EO * 8, 0, dead);
          signal_flag(&g_flags[(FL_O + m) * 32]);
        }
      }
    } else {
      const bool isA = warp == 0;
      uint32_t fb, eb, dst, par;
      {
        const uint32_t off = isA ? 0 : 8192, bytes = isA ? 8192 : 16384;
        int slot = 0;
        par = 0;
        fb = bars + B_FULL256 * 8; eb = bars + B_EMPTY256 * 8;
        dst = sb + RING + 2 * 24576 + off;
#pragma unroll 1
        for (int n = 6; n < 64; n++) {
          if (isA && n == 32) { mbar_wait(bars + (B_FLAG + 0) * 8, 0, dead); }
          mbar_wait(eb, par, dead);
          const int kc = (n & 31) * 32;
          if (elect_one()) {
            mbar_expect_tx(fb, bytes);
            if (isA) tma_load(dst, n < 32 ? &maps.x32 : &maps.y32, fb, kc, m * 128);
            else if (n < 32) tma_load4(dst, &maps.wkv32, fb, kc, j * 2);
            else tma_load3(dst, &maps.w1a32, fb, kc, j * 7);
          }
          fb += 8; eb += 8; dst += 24576;
          if (++slot == 4) dst -= 6 * 24576;
          if (slot == 6) { slot = 0; fb -= 48; eb -= 48; par ^= 1; }
        }
      }
      {
        const uint32_t off = isA ? 0 : 16384, bytes = isA ? 16384 : 24576;
#pragma unroll 1
        for (int n = 0; n < 16; n++) {
          const int slot = n & 3, u = n >> 2;
          if (u == 0) {
            if (slot == 0) { mbar_wait(bars + (B_EMPTY256 + 4) * 8, 1, dead); mbar_wait(bars + (B_EMPTY256 + 5) * 8, 1, dead); }
            else if (slot == 1) { mbar_wait(bars + (B_EMPTY256 + 0) * 8, 0, dead); mbar_wait(bars + (B_EMPTY256 + 1) * 8, 0, dead); }
            else if (slot == 2) mbar_wait(bars + (B_EMPTY256 + 2) * 8, 0, dead);
            else { mbar_wait(bars + (B_EMPTY256 + 3) * 8, 0, dead); if (!isA) mbar_wait(bars + B_E1DONE * 8, 0, dead); }
          } else {
            mbar_wait(bars + (B_EMPTY192 + slot) * 8, (u & 1) ^ 1, dead);
          }
          fb = bars + (B_FULL192 + slot) * 8;
          dst = sb + RING + slot * 40960 + off;
          if (elect_one()) {
            mbar_expect_tx(fb, bytes);
            if (isA) tma_load(dst, &maps.y, fb, n * 64, m * 128);
            else tma_load3(dst, &maps.w1b, fb, n * 64, j * 7 + 4);
          }
        }
      }
      {
        int slot = 0;
        fb = bars + B_FULL128 * 8; eb = bars + B_EMPTY128 * 8;
        dst = sb + RING + (isA ? 0 : 16384);
        par = 1;
        const CUtensorMap* mp = isA ? &maps.x : &maps.wq;
        int kc = 0, left = 16, seg = 0, jump_at = 0, jump = 0, cnt = 0;
#pragma unroll 1
        for (int n = 0; n < 88; n++) {
          if (n < 4) mbar_wait(bars + (B_EMPTY192 + n) * 8, 1, dead);
          if (left == 0) {
            seg++;
            if (isA) { mbar_wait(bars + (B_FLAG + seg) * 8, 0, dead); }
            cnt = 0;
            if (seg == 1) { mp = isA ? &maps.ho : &maps.w2; kc = 0; left = 32; jump_at = 4; jump = 192; }
            else if (seg == 2) { kc = 256; left = 24; jump_at = 3; jump = 256; }
            else { mp = isA ? &maps.ho : &maps.wo; kc = isA ? F : 0; left = 16; jump_at = 0; }
          }
          mbar_wait(eb, par, dead);
          if (elect_one()) {
            mbar_expect_tx(fb, 16384);
            if (isA) tma_load(dst, mp, fb, kc, m * 128);
            else tma_load3(dst, mp, fb, kc, j * 2);
          }
          kc += 64; left--;
          if (++cnt == jump_at) { cnt = 0; kc += jump; }
          fb += 8; eb += 8; dst += 32768;
          if (++slot == 5) { slot = 0; fb -= 40; eb -= 40; dst -= 5 * 32768; par ^= 1; }
        }
      }
    }
  } else if (wg < 3) {
    asm volatile("setmaxnreg.inc.sync.aligned.u32 168;");
    asm volatile("bar.sync 0, 512;" ::: "memory");
    const int w = wg - 1, q = warp & 3, lane = tid & 31;
    int rel = (tid & 127) == 0;
    asm volatile("" : "+r"(rel));
    int slot = 0;
    uint32_t ph = 0;
    {
#pragma unroll 1
      for (int tile = 0; tile < 2; tile++) {
        float acc[128];
        mma_tile<0>(acc, sb, w, 32, slot, ph, dead, rel, LEAD256);
        reg_fence<128>(acc);
        mbar_wait(bars + B_STG_EMPTY * 8, (tile & 1) ^ 1, dead);
        dump_tile<8, 16>(acc + 64, sb + STG, w * 4 + q, lane, tile == 0);
        if (tile == 0) {
          mbar_wait(bars + B_AUX * 8, 0, dead);
          project_and_dump(acc, sb, sb + WPHI1, w * 4 + q, lane);
        } else {
          dump_tile<0, 8>(acc, sb + STG, w * 4 + q, lane, false);
        }
        {
          fence_async_smem();
          __syncwarp();
          if (lane == 0) mbar_arrive(bars + B_STG_FULL * 8);
        }
      }
      {
        float a3[96];
        slot = 0; ph = 0;
        mma_tile<1>(a3, sb, w, 16, slot, ph, dead, rel, LEAD192);
        reg_fence<96>(a3);
        slot = 0; ph = 0;
        mbar_wait(bars + B_STG_EMPTY * 8, 1, dead);
        dump_tile<0, 12>(a3, sb + STG, w * 4 + q, lane, false);
        {
          fence_async_smem();
          __syncwarp();
          if (lane == 0) mbar_arrive(bars + B_STG_FULL * 8);
        }
      }
#pragma unroll 1
      for (int tile = 0; tile < 2; tile++) {
        float acc[64];
        mma_tile<2>(acc, sb, w, tile == 0 ? 16 : 72, slot, ph, dead, rel, tile == 0 ? LEAD_Q : LEAD_OUT);
        reg_fence<64>(acc);
        mbar_wait(bars + B_STG_EMPTY * 8, tile, dead);
        if (tile == 1) {
          const int r0 = w * 64 + q * 16 + (lane >> 2);
          float s0, s1;
          asm volatile("ld.shared.f32 %0, [%1];" : "=f"(s0) : "r"(sb + GVEC + r0 * 4));
          asm volatile("ld.shared.f32 %0, [%1];" : "=f"(s1) : "r"(sb + GVEC + (r0 + 8) * 4));
          s0 = 1.0f - s0; s1 = 1.0f - s1;
#pragma unroll
          for (int b = 0; b < 16; b++) {
            uint32_t bv;
            asm volatile("ld.shared.u32 %0, [%1];" : "=r"(bv) : "r"(sb + B2S + b * 16 + (lane & 3) * 4));
            const float b0 = bf_lo(bv), b1 = bf_hi(bv);
            acc[4 * b + 0] = fmaf(s0, b0, acc[4 * b + 0]);
            acc[4 * b + 1] = fmaf(s0, b1, acc[4 * b + 1]);
            acc[4 * b + 2] = fmaf(s1, b0, acc[4 * b + 2]);
            acc[4 * b + 3] = fmaf(s1, b1, acc[4 * b + 3]);
          }
        }
        if (tile == 0) {
          mbar_wait(bars + B_AUX * 8, 1, dead);
          project_and_dump(acc, sb, sb + WPHI2, w * 4 + q, lane);
          __syncwarp();
          if (lane == 0) mbar_arrive(bars + B_STG_FULL * 8);
        } else {
          dump_tile<0, 8>(acc, sb + STG, w * 4 + q, lane, false);
        }
      }
      {
        __syncwarp();
        const int rr0 = w * 64 + q * 16 + (lane >> 4), cc = lane & 15;
        __nv_bfloat16* og = reinterpret_cast<__nv_bfloat16*>(ptrs.out) + (size_t)(m * 128 + rr0) * D + j * 128 + cc * 8;
        uint4 v[8];
#pragma unroll
        for (int i = 0; i < 8; i++) {
          const int rr = rr0 + i * 2;
          asm volatile("ld.shared.v4.u32 {%0, %1, %2, %3}, [%4];" : "=r"(v[i].x), "=r"(v[i].y), "=r"(v[i].z), "=r"(v[i].w)
                       : "r"(sb + STG + (cc >> 3) * 16384 + rr * 128 + (((cc & 7) ^ (rr & 7)) << 4)) : "memory");
        }
        {
#pragma unroll
          for (int i = 0; i < 8; i++) *reinterpret_cast<uint4*>(og + (size_t)i * 2 * D) = v[i];
        }
      }
    }
  } else {
    asm volatile("setmaxnreg.inc.sync.aligned.u32 152;");
    asm volatile("bar.sync 0, 512;" ::: "memory");
    const int t = tid - 384, q = warp & 3, lane = t & 31;
    asm volatile("st.shared.v2.u32 [%0], {%1, %1};" ::"r"(sb + ONES + t * 8), "r"(0x3f803f80u) : "memory");
    mbar_wait(bars + (B_FULL256 + 0) * 8, 0, dead);
    {
      uint4 gw[4];
#pragma unroll
      for (int i = 0; i < 4; i++) gw[i] = __ldg(reinterpret_cast<const uint4*>(ptrs.gate_w + i * 256 + lane * 8));
      {
        uint4 xa[4][4];
        const int row0 = m * 128 + j * 16 + q * 4;
#pragma unroll
        for (int r = 0; r < 4; r++)
#pragma unroll
          for (int i = 0; i < 4; i++) {
            xa[r][i] = __ldg(reinterpret_cast<const uint4*>(ptrs.ax + (size_t)(row0 + r) * D + i * 256 + lane * 8));
          }
#pragma unroll
        for (int r = 0; r < 4; r++) {
          float v[32];
          float sum = 0.f, dot = 0.f;
#pragma unroll
          for (int i = 0; i < 4; i++) {
            const uint32_t* pa = reinterpret_cast<const uint32_t*>(&xa[r][i]);
            const uint32_t* pg = reinterpret_cast<const uint32_t*>(&gw[i]);
#pragma unroll
            for (int e = 0; e < 4; e++) {
              v[i * 8 + 2 * e] = bf_lo(pa[e]);
              v[i * 8 + 2 * e + 1] = bf_hi(pa[e]);
              sum += v[i * 8 + 2 * e] + v[i * 8 + 2 * e + 1];
              dot = fmaf(v[i * 8 + 2 * e], bf_lo(pg[e]), dot);
              dot = fmaf(v[i * 8 + 2 * e + 1], bf_hi(pg[e]), dot);
            }
          }
#pragma unroll
          for (int o = 16; o > 0; o >>= 1) {
            sum += __shfl_xor_sync(0xffffffffu, sum, o);
            dot += __shfl_xor_sync(0xffffffffu, dot, o);
          }
          const float mean = sum * (1.0f / D);
          float var = 0.f;
#pragma unroll
          for (int i = 0; i < 32; i++) { v[i] -= mean; var = fmaf(v[i], v[i], var); }
#pragma unroll
          for (int o = 16; o > 0; o >>= 1) var += __shfl_xor_sync(0xffffffffu, var, o);
          const float rstd = 1.0f / sqrtf(var * (1.0f / D) + 1e-5f);
#pragma unroll
          for (int i = 0; i < 4; i++) {
            uint4 o4;
            o4.x = pack_bf16(v[i * 8 + 0] * rstd, v[i * 8 + 1] * rstd);
            o4.y = pack_bf16(v[i * 8 + 2] * rstd, v[i * 8 + 3] * rstd);
            o4.z = pack_bf16(v[i * 8 + 4] * rstd, v[i * 8 + 5] * rstd);
            o4.w = pack_bf16(v[i * 8 + 6] * rstd, v[i * 8 + 7] * rstd);
            *reinterpret_cast<uint4*>(g_y + (size_t)(row0 + r) * D + i * 256 + lane * 8) = o4;
          }
          if (lane == 0) g_gate[row0 + r] = 1.0f / (1.0f + __expf(-dot));
        }
      }
      __syncwarp();
      if (lane == 0) mbar_arrive(bars + B_LNW * 8);
      mbar_wait(bars + (B_FLAG + 0) * 8, 0, dead);
      const float g = __ldcg(&g_gate[m * 128 + t]);
      asm volatile("st.shared.f32 [%0], %1;" ::"r"(sb + GVEC + t * 4), "f"(g) : "memory");
      if (t < 16) {
        const uint4 bb = __ldg(reinterpret_cast<const uint4*>(ptrs.b2 + j * 128) + t);
        *reinterpret_cast<uint4*>(smem_raw + B2S + t * 16) = bb;
      }
      fence_async_smem();
      named_bar(1);
    }
    mbar_wait(bars + B_STG_FULL * 8, 0, dead);
    {
      const int x = lane & 7, hi = lane >> 4;
      const int srow = q * 16 + x + ((lane >> 3) & 1) * 8;
#pragma unroll 1
      for (int c = 0; c < 2; c++) {
        const uint32_t kch = sb + STG + c * 16384;
        float pk[2][2][16];
        {
          uint32_t a[2][2][2][4];
#pragma unroll
          for (int hl = 0; hl < 2; hl++)
#pragma unroll
            for (int rh = 0; rh < 2; rh++)
#pragma unroll
              for (int s = 0; s < 2; s++)
                ldsm4(kch + (rh * 64 + srow) * 128 + (((hl * 4 + s * 2 + hi) ^ x) << 4), a[hl][rh][s]);
#pragma unroll
          for (int hl = 0; hl < 2; hl++)
#pragma unroll
            for (int rh = 0; rh < 2; rh++)
#pragma unroll
              for (int s = 0; s < 2; s++)
#pragma unroll
                for (int e = 0; e < 4; e++) {
                  pk[hl][rh][8 * s + 2 * e] = bf_lo(a[hl][rh][s][e]);
                  pk[hl][rh][8 * s + 2 * e + 1] = bf_hi(a[hl][rh][s][e]);
                }
        }
        float kv[2][20];
        uint32_t at[8][4];
        uint32_t P[2][4][2], Nn[2][4][2];
        auto put_phi = [&](uint32_t buf) {
#pragma unroll
          for (int rh = 0; rh < 2; rh++) {
            const uint32_t rb = buf + (rh * 64 + srow) * 128;
            stsm4(rb + (((0 + hi) ^ x) << 4), P[rh][0][0], P[rh][0][1], P[rh][1][0], P[rh][1][1]);
            stsm4(rb + (((2 + hi) ^ x) << 4), P[rh][2][0], P[rh][2][1], P[rh][3][0], P[rh][3][1]);
            stsm4(rb + (((4 + hi) ^ x) << 4), Nn[rh][0][0], Nn[rh][0][1], Nn[rh][1][0], Nn[rh][1][1]);
            stsm4(rb + (((6 + hi) ^ x) << 4), Nn[rh][2][0], Nn[rh][2][1], Nn[rh][3][0], Nn[rh][3][1]);
          }
        };
        auto pull_phi_t = [&](uint32_t buf) {
#pragma unroll
          for (int s = 0; s < 8; s++)
            ldsm4t(buf + (s * 16 + x + hi * 8) * 128 + (((2 * q + ((lane >> 3) & 1)) ^ x) << 4), at[s]);
        };
        auto kv_issue = [&](float* acc_, int hl) {
          const uint32_t vs = sb + STG + 32768 + (2 * c + hl) * 8192;
          uint64_t db = make_desc(vs, sb + ONES - vs, 512, 2);
          wg_fence();
#pragma unroll
          for (int s = 0; s < 8; s++) {
            if (s == 0) wgmma_rs_n40_tb1_init(acc_, at[s][0], at[s][1], at[s][2], at[s][3], db);
            else wgmma_rs_n40_tb1(acc_, at[s][0], at[s][1], at[s][2], at[s][3], db);
            db += 64 - (64ull << 16);
          }
          wg_commit();
        };
        auto kv_store = [&](const float* acc_, int hl) {
          const int head = j * 4 + 2 * c + hl;
          const int f = q * 16 + (lane >> 2);
          float* dst = g_kvp + ((size_t)(m * 32 + head) * 64 + f) * 32 + (lane & 3) * 2;
#pragma unroll
          for (int b = 0; b < 4; b++) {
            *reinterpret_cast<float2*>(dst + b * 8) = make_float2(acc_[4 * b], acc_[4 * b + 1]);
            *reinterpret_cast<float2*>(dst + 8 * 32 + b * 8) = make_float2(acc_[4 * b + 2], acc_[4 * b + 3]);
          }
          if ((lane & 3) == 0) {
            g_zp[(m * 32 + head) * 64 + f] = acc_[16];
            g_zp[(m * 32 + head) * 64 + f + 8] = acc_[18];
          }
        };
        using P1 = uint32_t (*)[1][4][2];
        dual_softmax<2>(pk[0], P, Nn);
        const uint32_t buf1 = sb + STG;
        put_phi(kch);
        named_bar(1);
        pull_phi_t(kch);
        dual_softmax<1>(*reinterpret_cast<float (*)[1][16]>(&pk[1][0]), *reinterpret_cast<P1>(&P[0]), *reinterpret_cast<P1>(&Nn[0]));
        kv_issue(kv[0], 0);
        dual_softmax<1>(*reinterpret_cast<float (*)[1][16]>(&pk[1][1]), *reinterpret_cast<P1>(&P[1]), *reinterpret_cast<P1>(&Nn[1]));
        if (c == 0) named_bar(1);
        put_phi(buf1);
        wg_wait<0>();
        reg_fence<20>(kv[0]);
        named_bar(1);
        pull_phi_t(buf1);
        kv_store(kv[0], 0);
        kv_issue(kv[1], 1);
        wg_wait<0>();
        reg_fence<20>(kv[1]);
        if (c == 1 && lane == 0) mbar_arrive(bars + B_STG_EMPTY * 8);
        kv_store(kv[1], 1);
      }
      __syncwarp();
      if (lane == 0) mbar_arrive(bars + B_E1W * 8);
    }
#pragma unroll 1
    for (int e = 0; e < 2; e++) {
      mbar_wait(bars + B_STG_FULL * 8, e ^ 1, dead);
      epi_gelu(sb, bars, ptrs.b1, g_ho + (size_t)m * 128 * KHO, j * 448 + e * 256, 4 - e, 2 - e, t);
      if (e == 0) {
        mbar_wait(bars + B_KVPR * 8, 0, dead);
        int tt = t;
        asm volatile("" : "+r"(tt));
        const int head = j * 4 + (m >> 2);
        const int f = (m & 3) * 16 + (tt >> 3), dq = tt & 7;
        const float* pk_ = g_kvp + (head * 64 + f) * 32 + dq * 4;
        const float* pz_ = g_zp + head * 64 + f;
        float4 s4 = make_float4(0.f, 0.f, 0.f, 0.f);
        float zs = 0.f;
#pragma unroll
        for (int mm = 0; mm < 16; mm++) {
          const float4 v = __ldcg(reinterpret_cast<const float4*>(pk_ + mm * (32 * 64 * 32)));
          s4.x += v.x; s4.y += v.y; s4.z += v.z; s4.w += v.w;
          zs += __ldcg(pz_ + mm * (32 * 64));
        }
        __nv_bfloat16* img = g_kvimg + head * 40 * 64;
        const float sv[4] = {s4.x, s4.y, s4.z, s4.w};
#pragma unroll
        for (int ee = 0; ee < 4; ee++) {
          const int n = dq * 4 + ee;
          img[n * 64 + (((f >> 3) ^ (n & 7)) << 3) + (f & 7)] = __float2bfloat16(sv[ee]);
        }
        if (dq == 0) img[32 * 64 + f] = __float2bfloat16(zs);
        __syncwarp();
        if (lane == 0) mbar_arrive(bars + B_RW * 8);
      }
    }
    named_bar(1);
    mbar_wait(bars + B_KVFR * 8, 0, dead);
    {
      const char* src = reinterpret_cast<const char*>(g_kvimg + j * 4 * 40 * 64);
#pragma unroll
      for (int i = 0; i < 10; i++) cp_async16(sb + KVIMG + (i * 128 + t) * 16, src + (i * 128 + t) * 16);
      asm volatile("cp.async.wait_all;" ::: "memory");
    }
    fence_async_smem();
    named_bar(1);
    mbar_wait(bars + B_STG_FULL * 8, 1, dead);
    {
      const int x = lane & 7, hi = lane >> 4;
      const int srow = q * 16 + x + ((lane >> 3) & 1) * 8;
#pragma unroll 1
      for (int it = 0; it < 4; it++) {
        const int c = it >> 1, rh = it & 1;
        const uint32_t qch = sb + STG + c * 16384 + rh * 8192;
        float pq[2][16];
        {
          uint32_t a[2][2][4];
#pragma unroll
          for (int hl = 0; hl < 2; hl++)
#pragma unroll
            for (int s = 0; s < 2; s++) ldsm4(qch + srow * 128 + (((hl * 4 + s * 2 + hi) ^ x) << 4), a[hl][s]);
#pragma unroll
          for (int hl = 0; hl < 2; hl++)
#pragma unroll
            for (int s = 0; s < 2; s++)
#pragma unroll
              for (int e = 0; e < 4; e++) {
                pq[hl][8 * s + 2 * e] = bf_lo(a[hl][s][e]);
                pq[hl][8 * s + 2 * e + 1] = bf_hi(a[hl][s][e]);
              }
        }
        uint32_t P[2][4][2], Nn[2][4][2];
        dual_softmax<2>(pq, P, Nn);
        float o[2][20];
        wg_fence();
#pragma unroll
        for (int hl = 0; hl < 2; hl++) {
          const uint32_t img = sb + KVIMG + (2 * c + hl) * 5120;
          wgmma_rs_n40_tb0_init(o[hl], P[hl][0][0], P[hl][0][1], P[hl][1][0], P[hl][1][1], make_desc(img + 0, 16, 1024, 1));
          wgmma_rs_n40_tb0(o[hl], P[hl][2][0], P[hl][2][1], P[hl][3][0], P[hl][3][1], make_desc(img + 32, 16, 1024, 1));
          wgmma_rs_n40_tb0(o[hl], Nn[hl][0][0], Nn[hl][0][1], Nn[hl][1][0], Nn[hl][1][1], make_desc(img + 64, 16, 1024, 1));
          wgmma_rs_n40_tb0(o[hl], Nn[hl][2][0], Nn[hl][2][1], Nn[hl][3][0], Nn[hl][3][1], make_desc(img + 96, 16, 1024, 1));
        }
        wg_commit();
        wg_wait<0>();
        reg_fence<20>(o[0]);
        reg_fence<20>(o[1]);
        const int r0 = rh * 64 + q * 16 + (lane >> 2);
        float g0, g1;
        asm volatile("ld.shared.f32 %0, [%1];" : "=f"(g0) : "r"(sb + GVEC + r0 * 4));
        asm volatile("ld.shared.f32 %0, [%1];" : "=f"(g1) : "r"(sb + GVEC + (r0 + 8) * 4));
#pragma unroll
        for (int hl = 0; hl < 2; hl++) {
          const float d0 = __shfl_sync(0xffffffffu, o[hl][16], lane & ~3);
          const float d1 = __shfl_sync(0xffffffffu, o[hl][18], lane & ~3);
          const float s0 = g0 * rcp(d0 + 1e-6f), s1 = g1 * rcp(d1 + 1e-6f);
          const uint32_t rb = qch + srow * 128;
          stsm4(rb + (((hl * 4 + 0 + hi) ^ x) << 4), pack_bf16(o[hl][0] * s0, o[hl][1] * s0), pack_bf16(o[hl][2] * s1, o[hl][3] * s1),
                pack_bf16(o[hl][4] * s0, o[hl][5] * s0), pack_bf16(o[hl][6] * s1, o[hl][7] * s1));
          stsm4(rb + (((hl * 4 + 2 + hi) ^ x) << 4), pack_bf16(o[hl][8] * s0, o[hl][9] * s0), pack_bf16(o[hl][10] * s1, o[hl][11] * s1),
                pack_bf16(o[hl][12] * s0, o[hl][13] * s0), pack_bf16(o[hl][14] * s1, o[hl][15] * s1));
        }
        __syncwarp();
        {
          __nv_bfloat16* og = g_ho + (size_t)(m * 128 + rh * 64 + q * 16 + (lane >> 3)) * KHO + F + j * 128 + c * 64 + (lane & 7) * 8;
#pragma unroll
          for (int i = 0; i < 4; i++) {
            const int rr = q * 16 + i * 4 + (lane >> 3);
            uint4 v;
            asm volatile("ld.shared.v4.u32 {%0, %1, %2, %3}, [%4];" : "=r"(v.x), "=r"(v.y), "=r"(v.z), "=r"(v.w)
                         : "r"(qch + rr * 128 + (((lane & 7) ^ (rr & 7)) << 4)) : "memory");
            *reinterpret_cast<uint4*>(og + (size_t)i * 4 * KHO) = v;
          }
        }
      }
      __syncwarp();
      if (lane == 0) { mbar_arrive(bars + B_STG_EMPTY * 8); mbar_arrive(bars + B_EO * 8); }
    }
  }
}

typedef CUresult (*EncodeFn)(CUtensorMap*, CUtensorMapDataType, cuuint32_t, void*, const cuuint64_t*, const cuuint64_t*,
                             const cuuint32_t*, const cuuint32_t*, CUtensorMapInterleave, CUtensorMapSwizzle,
                             CUtensorMapL2promotion, CUtensorMapFloatOOBfill);

static void make_map(EncodeFn fn, CUtensorMap* m, const void* ptr, uint64_t cols, uint64_t rows, uint32_t bc, uint32_t br,
                     CUtensorMapSwizzle swz) {
  cuuint64_t dims[2] = {cols, rows};
  cuuint64_t strides[1] = {cols * 2};
  cuuint32_t box[2] = {bc, br};
  cuuint32_t es[2] = {1, 1};
  fn(m, CU_TENSOR_MAP_DATA_TYPE_BFLOAT16, 2, const_cast<void*>(ptr), dims, strides, box, es, CU_TENSOR_MAP_INTERLEAVE_NONE,
     swz, CU_TENSOR_MAP_L2_PROMOTION_L2_128B, CU_TENSOR_MAP_FLOAT_OOB_FILL_NONE);
}

static void make_map_w(EncodeFn fn, CUtensorMap* m, const void* ptr, uint64_t cols, uint64_t nchunks, uint64_t rows, uint32_t bk,
                       uint32_t nch) {
  cuuint64_t dims[3] = {64, rows, nchunks};
  cuuint64_t strides[2] = {cols * 2, 128};
  cuuint32_t box[3] = {64, bk, nch};
  cuuint32_t es[3] = {1, 1, 1};
  fn(m, CU_TENSOR_MAP_DATA_TYPE_BFLOAT16, 3, const_cast<void*>(ptr), dims, strides, box, es, CU_TENSOR_MAP_INTERLEAVE_NONE,
     CU_TENSOR_MAP_SWIZZLE_128B, CU_TENSOR_MAP_L2_PROMOTION_L2_128B, CU_TENSOR_MAP_FLOAT_OOB_FILL_NONE);
}

}

extern "C" void kernel_launch(void* const* d_in, const int* in_sizes, int n_in, void* d_out, int out_size) {
  using namespace gm;
  (void)in_sizes; (void)n_in; (void)out_size;
  static EncodeFn enc = nullptr;
  static void *p_y = nullptr, *p_ho = nullptr;
  if (!enc) {
    void* p = nullptr;
    cudaDriverEntryPointQueryResult qr;
    cudaGetDriverEntryPoint("cuTensorMapEncodeTiled", &p, cudaEnableDefault, &qr);
    enc = (EncodeFn)p;
    cudaGetSymbolAddress(&p_y, g_y);
    cudaGetSymbolAddress(&p_ho, g_ho);
    cudaFuncSetAttribute(fused_kernel, cudaFuncAttributeMaxDynamicSharedMemorySize, (int)SMEM_BYTES);
  }
  const __nv_bfloat16* Ax = (const __nv_bfloat16*)d_in[0];
  const __nv_bfloat16* wqkv = (const __nv_bfloat16*)d_in[1];
  const __nv_bfloat16* wphi = (const __nv_bfloat16*)d_in[2];
  const __nv_bfloat16* wo = (const __nv_bfloat16*)d_in[3];
  const __nv_bfloat16* w1 = (const __nv_bfloat16*)d_in[5];
  const __nv_bfloat16* b1 = (const __nv_bfloat16*)d_in[6];
  const __nv_bfloat16* w2 = (const __nv_bfloat16*)d_in[7];
  const __nv_bfloat16* b2 = (const __nv_bfloat16*)d_in[8];
  const __nv_bfloat16* gate_w = (const __nv_bfloat16*)d_in[9];
  Maps maps;
  make_map(enc, &maps.x32, Ax, D, S, 32, 128, CU_TENSOR_MAP_SWIZZLE_64B);
  make_map(enc, &maps.y32, p_y, D, S, 32, 128, CU_TENSOR_MAP_SWIZZLE_64B);
  make_map(enc, &maps.x, Ax, D, S, 64, 128, CU_TENSOR_MAP_SWIZZLE_128B);
  make_map(enc, &maps.y, p_y, D, S, 64, 128, CU_TENSOR_MAP_SWIZZLE_128B);
  make_map(enc, &maps.ho, p_ho, KHO, S, 64, 128, CU_TENSOR_MAP_SWIZZLE_128B);
  {
    cuuint64_t dims[4] = {64, (cuuint64_t)D, 16, 2};
    cuuint64_t strides[3] = {3 * D * 2, 128, D * 2};
    cuuint32_t box[4] = {64, 32, 2, 2};
    cuuint32_t es[4] = {1, 1, 1, 1};
    enc(&maps.wkv32, CU_TENSOR_MAP_DATA_TYPE_BFLOAT16, 4, const_cast<__nv_bfloat16*>(wqkv + D), dims, strides, box, es,
        CU_TENSOR_MAP_INTERLEAVE_NONE, CU_TENSOR_MAP_SWIZZLE_128B, CU_TENSOR_MAP_L2_PROMOTION_L2_128B, CU_TENSOR_MAP_FLOAT_OOB_FILL_NONE);
  }
  make_map_w(enc, &maps.w1a32, w1, F, F / 64, D, 32, 4);
  make_map_w(enc, &maps.wq, wqkv, 3 * D, 3 * D / 64, D, 64, 2);
  make_map_w(enc, &maps.w1b, w1, F, F / 64, D, 64, 3);
  make_map_w(enc, &maps.w2, w2, D, D / 64, F, 64, 2);
  make_map_w(enc, &maps.wo, wo, D, D / 64, D, 64, 2);
  Ptrs ptrs{Ax, gate_w, b1, b2, wphi, d_out};
  fused_kernel<<<NCTA, NTHREADS, SMEM_BYTES, cudaStreamPerThread>>>(maps, ptrs);
}
```
